```python
import torch

def _softmax(x, axis=-1):
    return torch.softmax(x, dim=axis)
def _gelu(x):
    return torch.nn.functional.gelu(x, approximate="tanh")
def _silu(x):
    return torch.nn.functional.silu(x)
def _sigmoid(x):
    return torch.sigmoid(x)
def _layernorm(x, axis=-1, eps=1e-5):
    m = x.mean(dim=axis, keepdim=True)
    v = x.var(dim=axis, keepdim=True, unbiased=False)
    return (x - m) / torch.sqrt(v + eps)
def _scatter_add(tgt, idx, src, axis=0):
    return tgt.clone().index_add_(axis, idx, src)
def _segment_sum(src, seg, n):
    out = torch.zeros((n,) + src.shape[1:], dtype=src.dtype)
    return out.index_add_(0, seg, src)
def _pad(x, pw):
    flat = tuple(v for pair in reversed(pw) for v in pair)
    return torch.nn.functional.pad(x, flat)

kernel_name = 'parallel_sum__sliding_block__mixer_channel_mlp__prompt'

def setup_inputs():

    _w = (lambda a: (lambda t: t.to(torch.bfloat16) if t.is_floating_point() else t)(torch.as_tensor(a)))
    def _A_setup():
        B, S, D = 1, 2048, 512
        return {
            "x": _w((lambda *s: torch.randn(*s, dtype=torch.bfloat16) * 0.05)(B, S, D)),
            "wqkv": _w((lambda *s: torch.randn(*s, dtype=torch.bfloat16) * 0.05)(D, 3 * D)),
            "wo": _w((lambda *s: torch.randn(*s, dtype=torch.bfloat16) * 0.05)(D, D)),
        }
    _A_in = _A_setup()

    def _B_setup():
        B, S, D, F = 1, 2048, 512, 1376
        return {
            "x": _w((lambda *s: torch.randn(*s, dtype=torch.bfloat16) * 0.05)(B, S, D)),
            "w1": _w((lambda *s: torch.randn(*s, dtype=torch.bfloat16) * 3.2)(D, F) * (D ** -0.5)),
            "b1": _w((lambda *s: torch.randn(*s, dtype=torch.bfloat16) * 1.6)(F)),
            "w2": _w((lambda *s: torch.randn(*s, dtype=torch.bfloat16) * 0.2)(F, D) * (F ** -0.5)),
            "b2": _w((lambda *s: torch.randn(*s, dtype=torch.bfloat16) * 0.2)(D)),
        }
    _B_in = _B_setup()

    return {
        "A_x": _A_in["x"],
        "A_wqkv": _A_in["wqkv"],
        "A_wo": _A_in["wo"],
        "B_x": _B_in["x"],
        "B_w1": _B_in["w1"],
        "B_b1": _B_in["b1"],
        "B_w2": _B_in["w2"],
        "B_b2": _B_in["b2"],
    }

def reference(A_x, A_wqkv, A_wo, B_x, B_w1, B_b1, B_w2, B_b2):
    def _A_ref(x, wqkv, wo):
        B, S, D = x.shape
        H = 32; Dh = D // H; W = 256
        qkv = (lambda x, *d: x.permute(*d))((x @ wqkv).reshape(B, S, 3, H, Dh), 2, 0, 3, 1, 4)
        q, k, v = qkv[0], qkv[1], qkv[2]
        scores = torch.einsum("bhqd,bhkd->bhqk", q, k) * (Dh ** -0.5)
        idx = torch.arange(S)
        mask = (idx[:, None] - idx[None, :] >= 0) & (idx[:, None] - idx[None, :] < W)
        scores = torch.where(mask[None, None], scores, -1e9)
        p = _softmax(scores, axis=-1)
        o = torch.einsum("bhqk,bhkd->bhqd", p, v)
        return (lambda x, *d: x.permute(*d))(o, 0, 2, 1, 3).reshape(B, S, D) @ wo

    def _B_ref(x, w1, b1, w2, b2):
        y = _layernorm(x, axis=-1)
        h = _gelu(torch.einsum("bsd,df->bsf", y, w1) + b1)
        return torch.einsum("bsf,fd->bsd", h, w2) + b2

    x = A_x
    xn = _layernorm(x, axis=-1)
    return x + _A_ref(xn, A_wqkv, A_wo) + _B_ref(xn, B_w1, B_b1, B_w2, B_b2)
```

```cpp
#include <cuda_runtime.h>
#include <cuda_bf16.h>
#include <cuda.h>
#include <stdint.h>

namespace {

constexpr int D_ = 512;
constexpr int NCTA = 128, NTHR = 512;
constexpr float LN_EPS = 1e-5f;
constexpr int NG0 = 4;
constexpr int UA0 = 8 + NG0;

constexpr uint32_t OFF_X    = 0;
constexpr uint32_t OFF_WS   = 131072;
constexpr uint32_t WSLOT    = 12288;
constexpr uint32_t KVB      = 24832;
constexpr uint32_t OFF_KVB  = OFF_WS + 4 * WSLOT;
constexpr uint32_t OFF_KVA  = OFF_KVB + KVB;
constexpr uint32_t OFF_BAR  = OFF_KVA + KVB;
constexpr uint32_t OFF_CB1  = OFF_BAR + 1024;
constexpr uint32_t OFF_ZERO = OFF_CB1 + 1408;
constexpr uint32_t SMEM_BYTES = OFF_ZERO + 128;
constexpr uint32_t OFF_CS   = OFF_KVA;
constexpr uint32_t OFF_ST   = OFF_KVA + 1024;
constexpr uint32_t OFF_RED  = OFF_KVA + 2048;
constexpr uint32_t G2SLOT   = 36864;
constexpr uint32_t OFF_OUT  = 4 * G2SLOT;
constexpr uint32_t OFF_B2   = OFF_OUT + 16384;
enum { B_UF = 0, B_UE = 32, B_G2F = 64, B_KVF = 72, B_CB = 76, B_XT = 77,
       B_KD = 80, B_PREP = 83, B_OD = 84, B_QD = 88, B_XA = 89, B_QR = 90,
       B_G2E = 96, B_XF = 106, B_HD = 107, B_SR = 111, B_DONE = 112 };

struct PerG {
  uint8_t k[4 * 65536];
  uint32_t epoch[32];
  uint32_t kvcnt[18 * 8 + 16];
  uint8_t v0[4 * 32768];
  uint8_t v1[4 * 32768];
};
struct PerR {
  uint4 stat[64];
  uint32_t acnt[64];
  uint8_t a2[112 * 2048];
  uint4 ll[2][8 * 128];
};
struct Scratch {
  PerG G[8];
  PerR R[32];
  uint2 cs[(1536 + 1376) * 2];
};
__device__ __align__(128) Scratch g_scr;
__device__ __align__(128) const uint32_t g_ones[64] = {
#define O8 0x3F803F80u,0x3F803F80u,0x3F803F80u,0x3F803F80u,0x3F803F80u,0x3F803F80u,0x3F803F80u,0x3F803F80u
  O8, O8, O8, O8, O8, O8, O8, O8 };

constexpr uint32_t SPIN_LIMIT = 1u << 22;
__device__ __forceinline__ void mbar_init(uint32_t b, int c) { asm volatile("mbarrier.init.shared::cta.b64 [%0], %1;" ::"r"(b), "r"(c)); }
__device__ __forceinline__ void mbar_expect(uint32_t b, uint32_t bytes) { asm volatile("{\n.reg .pred p;\nelect.sync _|p, 0xffffffff;\n@p mbarrier.arrive.expect_tx.shared::cta.b64 _, [%0], %1;\n}" ::"r"(b), "r"(bytes) : "memory"); }
__device__ __forceinline__ void mbar_arrive(uint32_t b) { asm volatile("mbarrier.arrive.shared::cta.b64 _, [%0];" ::"r"(b) : "memory"); }
__device__ __forceinline__ void mbar_wait(uint32_t b, uint32_t ph) {
  asm volatile("{\n.reg .pred p;\nW: mbarrier.try_wait.parity.shared::cta.b64 p, [%0], %1;\n@!p bra W;\n}" ::"r"(b), "r"(ph) : "memory");
}
__device__ __forceinline__ void mbar_guard(uint32_t b) {
  asm volatile("{\n.reg .pred p;\n.reg .b32 n;\nmov.b32 n, 0;\n"
               "W: mbarrier.try_wait.parity.shared::cta.b64 p, [%0], 0, 4000;\n@p bra D;\n"
               "add.u32 n, n, 1;\nsetp.lt.u32 p, n, %1;\n@p bra W;\ntrap;\nD:\n}" ::"r"(b), "n"(SPIN_LIMIT / 4) : "memory");
}
__device__ __forceinline__ void tma2d(uint32_t dst, const CUtensorMap* tm, uint32_t bar, int c0, int c1) {
  asm volatile("{\n.reg .pred p;\nelect.sync _|p, 0xffffffff;\n@p cp.async.bulk.tensor.2d.shared::cluster.global.mbarrier::complete_tx::bytes [%0], [%1, {%3,%4}], [%2];\n}"
               ::"r"(dst), "l"(tm), "r"(bar), "r"(c0), "r"(c1) : "memory");
}
__device__ __forceinline__ void tma3d(uint32_t dst, const CUtensorMap* tm, uint32_t bar, int c0, int c1, int c2) {
  asm volatile("{\n.reg .pred p;\nelect.sync _|p, 0xffffffff;\n@p cp.async.bulk.tensor.3d.shared::cluster.global.mbarrier::complete_tx::bytes [%0], [%1, {%3,%4,%5}], [%2];\n}"
               ::"r"(dst), "l"(tm), "r"(bar), "r"(c0), "r"(c1), "r"(c2) : "memory");
}
__device__ __forceinline__ void tma4d(uint32_t dst, const CUtensorMap* tm, uint32_t bar, int c0, int c1, int c2, int c3) {
  asm volatile("{\n.reg .pred p;\nelect.sync _|p, 0xffffffff;\n@p cp.async.bulk.tensor.4d.shared::cluster.global.mbarrier::complete_tx::bytes [%0], [%1, {%3,%4,%5,%6}], [%2];\n}"
               ::"r"(dst), "l"(tm), "r"(bar), "r"(c0), "r"(c1), "r"(c2), "r"(c3) : "memory");
}
__device__ __forceinline__ void tma5d(uint32_t dst, const CUtensorMap* tm, uint32_t bar, int c0, int c1, int c2, int c3, int c4) {
  asm volatile("{\n.reg .pred p;\nelect.sync _|p, 0xffffffff;\n@p cp.async.bulk.tensor.5d.shared::cluster.global.mbarrier::complete_tx::bytes [%0], [%1, {%3,%4,%5,%6,%7}], [%2];\n}"
               ::"r"(dst), "l"(tm), "r"(bar), "r"(c0), "r"(c1), "r"(c2), "r"(c3), "r"(c4) : "memory");
}
__device__ __forceinline__ void tma3d_store(const CUtensorMap* tm, uint32_t src, int c0, int c1, int c2) {
  asm volatile("cp.async.bulk.tensor.3d.global.shared::cta.bulk_group [%0, {%2,%3,%4}], [%1];"
               ::"l"(tm), "r"(src), "r"(c0), "r"(c1), "r"(c2) : "memory");
}
__device__ __forceinline__ void bulk_ld(uint32_t dst, const void* src, uint32_t bytes, uint32_t bar) {
  asm volatile("{\n.reg .pred p;\nelect.sync _|p, 0xffffffff;\n@p cp.async.bulk.shared::cluster.global.mbarrier::complete_tx::bytes [%0], [%1], %2, [%3];\n}"
               ::"r"(dst), "l"(src), "r"(bytes), "r"(bar) : "memory");
}
__device__ __forceinline__ void l2_prefetch(const void* src, uint32_t bytes) {
  asm volatile("{\n.reg .pred p;\nelect.sync _|p, 0xffffffff;\n@p cp.async.bulk.prefetch.L2.global [%0], %1;\n}" ::"l"(src), "r"(bytes) : "memory");
}
__device__ __forceinline__ void fence_async_global() { asm volatile("fence.proxy.async.global;" ::: "memory"); }
__device__ __forceinline__ void fence_async_shared() { asm volatile("fence.proxy.async.shared::cta;" ::: "memory"); }
__device__ __forceinline__ void cnt_add_rel(uint32_t* f) { asm volatile("fence.release.gpu;\nred.relaxed.gpu.global.add.u32 [%0], 1;" ::"l"(f) : "memory"); }
__device__ __forceinline__ uint32_t ld_acq(const uint32_t* f) { uint32_t v; asm volatile("ld.acquire.gpu.global.u32 %0, [%1];" : "=r"(v) : "l"(f) : "memory"); return v; }
__device__ __forceinline__ void cnt_wait(const uint32_t* f, uint32_t target) {
  asm volatile("{\n.reg .pred p;\n.reg .b32 n, v;\nmov.b32 n, 0;\n"
               "W: ld.acquire.gpu.global.u32 v, [%0];\nsetp.eq.u32 p, v, %1;\n@p bra D;\n"
               "add.u32 n, n, 1;\nsetp.lt.u32 p, n, %2;\n@p bra W;\ntrap;\nD:\nfence.proxy.async.global;\n}" ::"l"(f), "r"(target), "n"(SPIN_LIMIT) : "memory");
}
template <int N> __device__ __forceinline__ void mbar_arrive_n(uint32_t b) { asm volatile("mbarrier.arrive.shared::cta.b64 _, [%0], %1;" ::"r"(b), "n"(N) : "memory"); }
__device__ __forceinline__ uint4 ld_rlx4(const uint4* p) {
  uint4 v;
  asm volatile("{\n.reg .b64 a, b;\nld.relaxed.gpu.global.v2.b64 {a, b}, [%4];\nmov.b64 {%0,%1}, a;\nmov.b64 {%2,%3}, b;\n}"
               : "=r"(v.x), "=r"(v.y), "=r"(v.z), "=r"(v.w) : "l"(p) : "memory");
  return v;
}
__device__ __forceinline__ uint4 ldg128(const void* p) {
  uint4 v; asm volatile("ld.global.nc.L1::no_allocate.v4.u32 {%0,%1,%2,%3}, [%4];" : "=r"(v.x), "=r"(v.y), "=r"(v.z), "=r"(v.w) : "l"(p)); return v;
}
__device__ __forceinline__ void wg_fence() { asm volatile("wgmma.fence.sync.aligned;" ::: "memory"); }
__device__ __forceinline__ void wg_commit() { asm volatile("wgmma.commit_group.sync.aligned;" ::: "memory"); }
template <int N> __device__ __forceinline__ void wg_wait() { asm volatile("wgmma.wait_group.sync.aligned %0;" ::"n"(N) : "memory"); }
template <int N> __device__ __forceinline__ void pin(float (&a)[N]) {
#pragma unroll
  for (int i = 0; i < N; i++) asm volatile("" : "+f"(a[i])::"memory");
}
__device__ __forceinline__ float ex2(float x) { float y; asm("ex2.approx.ftz.f32 %0, %1;" : "=f"(y) : "f"(x)); return y; }
__device__ __forceinline__ float tanh_ap(float x) { float y; asm("tanh.approx.f32 %0, %1;" : "=f"(y) : "f"(x)); return y; }
__device__ __forceinline__ uint32_t pack(float lo, float hi) { uint32_t r; asm("cvt.rn.bf16x2.f32 %0, %1, %2;" : "=r"(r) : "f"(hi), "f"(lo)); return r; }
__device__ __forceinline__ float bf_lo(uint32_t u) { return __uint_as_float(u << 16); }
__device__ __forceinline__ float bf_hi(uint32_t u) { return __uint_as_float(u & 0xFFFF0000u); }
__device__ __forceinline__ float2 lds64(uint32_t a) { float2 v; asm volatile("ld.shared.v2.f32 {%0,%1}, [%2];" : "=f"(v.x), "=f"(v.y) : "r"(a)); return v; }
__device__ __forceinline__ float4 lds128(uint32_t a) { float4 v; asm volatile("ld.shared.v4.f32 {%0,%1,%2,%3}, [%4];" : "=f"(v.x), "=f"(v.y), "=f"(v.z), "=f"(v.w) : "r"(a)); return v; }
__device__ __forceinline__ uint4 lds128u(uint32_t a) { uint4 v; asm volatile("ld.shared.v4.u32 {%0,%1,%2,%3}, [%4];" : "=r"(v.x), "=r"(v.y), "=r"(v.z), "=r"(v.w) : "r"(a)); return v; }
__device__ __forceinline__ uint32_t lds32u(uint32_t a) { uint32_t v; asm volatile("ld.shared.u32 %0, [%1];" : "=r"(v) : "r"(a)); return v; }
__device__ __forceinline__ void sts32u(uint32_t a, uint32_t v) { asm volatile("st.shared.u32 [%0], %1;" ::"r"(a), "r"(v) : "memory"); }
__device__ __forceinline__ float gelu_half(float h) {
  const float u = h * __fmaf_rn(h * h, 0.2854192648f, 1.5957691216f);
  return __fmaf_rn(h, tanh_ap(u), h);
}

template<int AOFF, uint32_t AHI, int BOFF, uint32_t BHI> __device__ __forceinline__ void wss192(float (&d)[96], uint32_t alo, uint32_t blo, uint32_t sd){
  asm volatile("{\n.reg .pred p;\n.reg .b32 la, lb;\n.reg .b64 da, db;\nsetp.ne.b32 p, %102, 0;\n"
   "add.s32 la, %96, %98;\nadd.s32 lb, %97, %100;\nmov.b64 da, {la, %99};\nmov.b64 db, {lb, %101};\n"
   "wgmma.mma_async.sync.aligned.m64n192k16.f32.bf16.bf16 {%0, %1, %2, %3, %4, %5, %6, %7, %8, %9, %10, %11, %12, %13, %14, %15, %16, %17, %18, %19, %20, %21, %22, %23, %24, %25, %26, %27, %28, %29, %30, %31, %32, %33, %34, %35, %36, %37, %38, %39, %40, %41, %42, %43, %44, %45, %46, %47, %48, %49, %50, %51, %52, %53, %54, %55, %56, %57, %58, %59, %60, %61, %62, %63, %64, %65, %66, %67, %68, %69, %70, %71, %72, %73, %74, %75, %76, %77, %78, %79, %80, %81, %82, %83, %84, %85, %86, %87, %88, %89, %90, %91, %92, %93, %94, %95}, da, db, p, 1, 1, 0, 1;\n}\n"
   : "+f"(d[0]), "+f"(d[1]), "+f"(d[2]), "+f"(d[3]), "+f"(d[4]), "+f"(d[5]), "+f"(d[6]), "+f"(d[7]), "+f"(d[8]), "+f"(d[9]), "+f"(d[10]), "+f"(d[11]), "+f"(d[12]), "+f"(d[13]), "+f"(d[14]), "+f"(d[15]), "+f"(d[16]), "+f"(d[17]), "+f"(d[18]), "+f"(d[19]), "+f"(d[20]), "+f"(d[21]), "+f"(d[22]), "+f"(d[23]), "+f"(d[24]), "+f"(d[25]), "+f"(d[26]), "+f"(d[27]), "+f"(d[28]), "+f"(d[29]), "+f"(d[30]), "+f"(d[31]), "+f"(d[32]), "+f"(d[33]), "+f"(d[34]), "+f"(d[35]), "+f"(d[36]), "+f"(d[37]), "+f"(d[38]), "+f"(d[39]), "+f"(d[40]), "+f"(d[41]), "+f"(d[42]), "+f"(d[43]), "+f"(d[44]), "+f"(d[45]), "+f"(d[46]), "+f"(d[47]), "+f"(d[48]), "+f"(d[49]), "+f"(d[50]), "+f"(d[51]), "+f"(d[52]), "+f"(d[53]), "+f"(d[54]), "+f"(d[55]), "+f"(d[56]), "+f"(d[57]), "+f"(d[58]), "+f"(d[59]), "+f"(d[60]), "+f"(d[61]), "+f"(d[62]), "+f"(d[63]), "+f"(d[64]), "+f"(d[65]), "+f"(d[66]), "+f"(d[67]), "+f"(d[68]), "+f"(d[69]), "+f"(d[70]), "+f"(d[71]), "+f"(d[72]), "+f"(d[73]), "+f"(d[74]), "+f"(d[75]), "+f"(d[76]), "+f"(d[77]), "+f"(d[78]), "+f"(d[79]), "+f"(d[80]), "+f"(d[81]), "+f"(d[82]), "+f"(d[83]), "+f"(d[84]), "+f"(d[85]), "+f"(d[86]), "+f"(d[87]), "+f"(d[88]), "+f"(d[89]), "+f"(d[90]), "+f"(d[91]), "+f"(d[92]), "+f"(d[93]), "+f"(d[94]), "+f"(d[95]) : "r"(alo), "r"(blo), "n"(AOFF), "n"(AHI), "n"(BOFF), "n"(BHI), "r"(sd));
}
template<int AOFF, uint32_t AHI, int BOFF, uint32_t BHI> __device__ __forceinline__ void wss96(float (&d)[48], uint32_t alo, uint32_t blo, uint32_t sd){
  asm volatile("{\n.reg .pred p;\n.reg .b32 la, lb;\n.reg .b64 da, db;\nsetp.ne.b32 p, %54, 0;\n"
   "add.s32 la, %48, %50;\nadd.s32 lb, %49, %52;\nmov.b64 da, {la, %51};\nmov.b64 db, {lb, %53};\n"
   "wgmma.mma_async.sync.aligned.m64n96k16.f32.bf16.bf16 {%0, %1, %2, %3, %4, %5, %6, %7, %8, %9, %10, %11, %12, %13, %14, %15, %16, %17, %18, %19, %20, %21, %22, %23, %24, %25, %26, %27, %28, %29, %30, %31, %32, %33, %34, %35, %36, %37, %38, %39, %40, %41, %42, %43, %44, %45, %46, %47}, da, db, p, 1, 1, 0, 1;\n}\n"
   : "+f"(d[0]), "+f"(d[1]), "+f"(d[2]), "+f"(d[3]), "+f"(d[4]), "+f"(d[5]), "+f"(d[6]), "+f"(d[7]), "+f"(d[8]), "+f"(d[9]), "+f"(d[10]), "+f"(d[11]), "+f"(d[12]), "+f"(d[13]), "+f"(d[14]), "+f"(d[15]), "+f"(d[16]), "+f"(d[17]), "+f"(d[18]), "+f"(d[19]), "+f"(d[20]), "+f"(d[21]), "+f"(d[22]), "+f"(d[23]), "+f"(d[24]), "+f"(d[25]), "+f"(d[26]), "+f"(d[27]), "+f"(d[28]), "+f"(d[29]), "+f"(d[30]), "+f"(d[31]), "+f"(d[32]), "+f"(d[33]), "+f"(d[34]), "+f"(d[35]), "+f"(d[36]), "+f"(d[37]), "+f"(d[38]), "+f"(d[39]), "+f"(d[40]), "+f"(d[41]), "+f"(d[42]), "+f"(d[43]), "+f"(d[44]), "+f"(d[45]), "+f"(d[46]), "+f"(d[47]) : "r"(alo), "r"(blo), "n"(AOFF), "n"(AHI), "n"(BOFF), "n"(BHI), "r"(sd));
}
template<int AOFF, uint32_t AHI, int BOFF, uint32_t BHI> __device__ __forceinline__ void wss80(float (&d)[40], uint32_t alo, uint32_t blo, uint32_t sd){
  asm volatile("{\n.reg .pred p;\n.reg .b32 la, lb;\n.reg .b64 da, db;\nsetp.ne.b32 p, %46, 0;\n"
   "add.s32 la, %40, %42;\nadd.s32 lb, %41, %44;\nmov.b64 da, {la, %43};\nmov.b64 db, {lb, %45};\n"
   "wgmma.mma_async.sync.aligned.m64n80k16.f32.bf16.bf16 {%0, %1, %2, %3, %4, %5, %6, %7, %8, %9, %10, %11, %12, %13, %14, %15, %16, %17, %18, %19, %20, %21, %22, %23, %24, %25, %26, %27, %28, %29, %30, %31, %32, %33, %34, %35, %36, %37, %38, %39}, da, db, p, 1, 1, 0, 1;\n}\n"
   : "+f"(d[0]), "+f"(d[1]), "+f"(d[2]), "+f"(d[3]), "+f"(d[4]), "+f"(d[5]), "+f"(d[6]), "+f"(d[7]), "+f"(d[8]), "+f"(d[9]), "+f"(d[10]), "+f"(d[11]), "+f"(d[12]), "+f"(d[13]), "+f"(d[14]), "+f"(d[15]), "+f"(d[16]), "+f"(d[17]), "+f"(d[18]), "+f"(d[19]), "+f"(d[20]), "+f"(d[21]), "+f"(d[22]), "+f"(d[23]), "+f"(d[24]), "+f"(d[25]), "+f"(d[26]), "+f"(d[27]), "+f"(d[28]), "+f"(d[29]), "+f"(d[30]), "+f"(d[31]), "+f"(d[32]), "+f"(d[33]), "+f"(d[34]), "+f"(d[35]), "+f"(d[36]), "+f"(d[37]), "+f"(d[38]), "+f"(d[39]) : "r"(alo), "r"(blo), "n"(AOFF), "n"(AHI), "n"(BOFF), "n"(BHI), "r"(sd));
}
template<int AOFF, uint32_t AHI, int BOFF, uint32_t BHI> __device__ __forceinline__ void wss128(float (&d)[64], uint32_t alo, uint32_t blo, uint32_t sd){
  asm volatile("{\n.reg .pred p;\n.reg .b32 la, lb;\n.reg .b64 da, db;\nsetp.ne.b32 p, %70, 0;\n"
   "add.s32 la, %64, %66;\nadd.s32 lb, %65, %68;\nmov.b64 da, {la, %67};\nmov.b64 db, {lb, %69};\n"
   "wgmma.mma_async.sync.aligned.m64n128k16.f32.bf16.bf16 {%0, %1, %2, %3, %4, %5, %6, %7, %8, %9, %10, %11, %12, %13, %14, %15, %16, %17, %18, %19, %20, %21, %22, %23, %24, %25, %26, %27, %28, %29, %30, %31, %32, %33, %34, %35, %36, %37, %38, %39, %40, %41, %42, %43, %44, %45, %46, %47, %48, %49, %50, %51, %52, %53, %54, %55, %56, %57, %58, %59, %60, %61, %62, %63}, da, db, p, 1, 1, 0, 1;\n}\n"
   : "+f"(d[0]), "+f"(d[1]), "+f"(d[2]), "+f"(d[3]), "+f"(d[4]), "+f"(d[5]), "+f"(d[6]), "+f"(d[7]), "+f"(d[8]), "+f"(d[9]), "+f"(d[10]), "+f"(d[11]), "+f"(d[12]), "+f"(d[13]), "+f"(d[14]), "+f"(d[15]), "+f"(d[16]), "+f"(d[17]), "+f"(d[18]), "+f"(d[19]), "+f"(d[20]), "+f"(d[21]), "+f"(d[22]), "+f"(d[23]), "+f"(d[24]), "+f"(d[25]), "+f"(d[26]), "+f"(d[27]), "+f"(d[28]), "+f"(d[29]), "+f"(d[30]), "+f"(d[31]), "+f"(d[32]), "+f"(d[33]), "+f"(d[34]), "+f"(d[35]), "+f"(d[36]), "+f"(d[37]), "+f"(d[38]), "+f"(d[39]), "+f"(d[40]), "+f"(d[41]), "+f"(d[42]), "+f"(d[43]), "+f"(d[44]), "+f"(d[45]), "+f"(d[46]), "+f"(d[47]), "+f"(d[48]), "+f"(d[49]), "+f"(d[50]), "+f"(d[51]), "+f"(d[52]), "+f"(d[53]), "+f"(d[54]), "+f"(d[55]), "+f"(d[56]), "+f"(d[57]), "+f"(d[58]), "+f"(d[59]), "+f"(d[60]), "+f"(d[61]), "+f"(d[62]), "+f"(d[63]) : "r"(alo), "r"(blo), "n"(AOFF), "n"(AHI), "n"(BOFF), "n"(BHI), "r"(sd));
}
template<int BOFF, uint32_t BHI> __device__ __forceinline__ void wrs128(float (&d)[64], const uint32_t (&a)[4], uint32_t blo, uint32_t sd){
  asm volatile("{\n.reg .pred p;\n.reg .b32 lb;\n.reg .b64 db;\nsetp.ne.b32 p, %71, 0;\n"
   "add.s32 lb, %68, %69;\nmov.b64 db, {lb, %70};\n"
   "wgmma.mma_async.sync.aligned.m64n128k16.f32.bf16.bf16 {%0, %1, %2, %3, %4, %5, %6, %7, %8, %9, %10, %11, %12, %13, %14, %15, %16, %17, %18, %19, %20, %21, %22, %23, %24, %25, %26, %27, %28, %29, %30, %31, %32, %33, %34, %35, %36, %37, %38, %39, %40, %41, %42, %43, %44, %45, %46, %47, %48, %49, %50, %51, %52, %53, %54, %55, %56, %57, %58, %59, %60, %61, %62, %63}, {%64,%65,%66,%67}, db, p, 1, 1, 1;\n}\n"
   : "+f"(d[0]), "+f"(d[1]), "+f"(d[2]), "+f"(d[3]), "+f"(d[4]), "+f"(d[5]), "+f"(d[6]), "+f"(d[7]), "+f"(d[8]), "+f"(d[9]), "+f"(d[10]), "+f"(d[11]), "+f"(d[12]), "+f"(d[13]), "+f"(d[14]), "+f"(d[15]), "+f"(d[16]), "+f"(d[17]), "+f"(d[18]), "+f"(d[19]), "+f"(d[20]), "+f"(d[21]), "+f"(d[22]), "+f"(d[23]), "+f"(d[24]), "+f"(d[25]), "+f"(d[26]), "+f"(d[27]), "+f"(d[28]), "+f"(d[29]), "+f"(d[30]), "+f"(d[31]), "+f"(d[32]), "+f"(d[33]), "+f"(d[34]), "+f"(d[35]), "+f"(d[36]), "+f"(d[37]), "+f"(d[38]), "+f"(d[39]), "+f"(d[40]), "+f"(d[41]), "+f"(d[42]), "+f"(d[43]), "+f"(d[44]), "+f"(d[45]), "+f"(d[46]), "+f"(d[47]), "+f"(d[48]), "+f"(d[49]), "+f"(d[50]), "+f"(d[51]), "+f"(d[52]), "+f"(d[53]), "+f"(d[54]), "+f"(d[55]), "+f"(d[56]), "+f"(d[57]), "+f"(d[58]), "+f"(d[59]), "+f"(d[60]), "+f"(d[61]), "+f"(d[62]), "+f"(d[63]) : "r"(a[0]), "r"(a[1]), "r"(a[2]), "r"(a[3]), "r"(blo), "n"(BOFF), "n"(BHI), "r"(sd));
}
template<int BOFF, int HOFF> __device__ __forceinline__ void wrs64_ini(float (&d)[32], const uint32_t (&a)[4], uint32_t blo, uint32_t bhi){
  asm volatile("{\n.reg .pred p;\n.reg .b32 lb, hb;\n.reg .b64 db;\nsetp.ne.b32 p, 0, 0;\n"
   "add.s32 lb, %36, %38;\nadd.s32 hb, %37, %39;\nmov.b64 db, {lb, hb};\n"
   "wgmma.mma_async.sync.aligned.m64n64k16.f32.bf16.bf16 {%0, %1, %2, %3, %4, %5, %6, %7, %8, %9, %10, %11, %12, %13, %14, %15, %16, %17, %18, %19, %20, %21, %22, %23, %24, %25, %26, %27, %28, %29, %30, %31}, {%32,%33,%34,%35}, db, p, 1, 1, 0;\n}\n"
   : "=f"(d[0]), "=f"(d[1]), "=f"(d[2]), "=f"(d[3]), "=f"(d[4]), "=f"(d[5]), "=f"(d[6]), "=f"(d[7]), "=f"(d[8]), "=f"(d[9]), "=f"(d[10]), "=f"(d[11]), "=f"(d[12]), "=f"(d[13]), "=f"(d[14]), "=f"(d[15]), "=f"(d[16]), "=f"(d[17]), "=f"(d[18]), "=f"(d[19]), "=f"(d[20]), "=f"(d[21]), "=f"(d[22]), "=f"(d[23]), "=f"(d[24]), "=f"(d[25]), "=f"(d[26]), "=f"(d[27]), "=f"(d[28]), "=f"(d[29]), "=f"(d[30]), "=f"(d[31]) : "r"(a[0]), "r"(a[1]), "r"(a[2]), "r"(a[3]), "r"(blo), "r"(bhi), "n"(BOFF), "n"(HOFF));
}
template<int BOFF, int HOFF> __device__ __forceinline__ void wrs24_acc(float (&d)[12], const uint32_t (&a)[4], uint32_t blo, uint32_t bhi){
  asm volatile("{\n.reg .pred p;\n.reg .b32 lb, hb;\n.reg .b64 db;\nsetp.ne.b32 p, 1, 0;\n"
   "add.s32 lb, %16, %18;\nadd.s32 hb, %17, %19;\nmov.b64 db, {lb, hb};\n"
   "wgmma.mma_async.sync.aligned.m64n24k16.f32.bf16.bf16 {%0, %1, %2, %3, %4, %5, %6, %7, %8, %9, %10, %11}, {%12,%13,%14,%15}, db, p, 1, 1, 1;\n}\n"
   : "+f"(d[0]), "+f"(d[1]), "+f"(d[2]), "+f"(d[3]), "+f"(d[4]), "+f"(d[5]), "+f"(d[6]), "+f"(d[7]), "+f"(d[8]), "+f"(d[9]), "+f"(d[10]), "+f"(d[11]) : "r"(a[0]), "r"(a[1]), "r"(a[2]), "r"(a[3]), "r"(blo), "r"(bhi), "n"(BOFF), "n"(HOFF));
}
template<int BOFF, int HOFF> __device__ __forceinline__ void wrs24_ini(float (&d)[12], const uint32_t (&a)[4], uint32_t blo, uint32_t bhi){
  asm volatile("{\n.reg .pred p;\n.reg .b32 lb, hb;\n.reg .b64 db;\nsetp.ne.b32 p, 0, 0;\n"
   "add.s32 lb, %16, %18;\nadd.s32 hb, %17, %19;\nmov.b64 db, {lb, hb};\n"
   "wgmma.mma_async.sync.aligned.m64n24k16.f32.bf16.bf16 {%0, %1, %2, %3, %4, %5, %6, %7, %8, %9, %10, %11}, {%12,%13,%14,%15}, db, p, 1, 1, 1;\n}\n"
   : "=f"(d[0]), "=f"(d[1]), "=f"(d[2]), "=f"(d[3]), "=f"(d[4]), "=f"(d[5]), "=f"(d[6]), "=f"(d[7]), "=f"(d[8]), "=f"(d[9]), "=f"(d[10]), "=f"(d[11]) : "r"(a[0]), "r"(a[1]), "r"(a[2]), "r"(a[3]), "r"(blo), "r"(bhi), "n"(BOFF), "n"(HOFF));
}


constexpr uint32_t HI_SW128 = (1024u >> 4) | (1u << 30);
constexpr uint32_t HI_SW64  = (512u >> 4) | (2u << 30);
constexpr uint32_t HI_A2    = (256u >> 4);
__device__ __forceinline__ uint32_t dlo(uint32_t addr) { return (addr & 0x3FFFFu) >> 4; }

__device__ __forceinline__ void exps(float (&s)[32]) {
#pragma unroll
  for (int j = 0; j < 32; j++) s[j] = ex2(s[j]);
}
__device__ __forceinline__ void packp(const float (&s)[32], uint32_t (&p)[4][4]) {
#pragma unroll
  for (int t = 0; t < 4; t++) {
    p[t][0] = pack(s[8 * t], s[8 * t + 1]); p[t][1] = pack(s[8 * t + 2], s[8 * t + 3]);
    p[t][2] = pack(s[8 * t + 4], s[8 * t + 5]); p[t][3] = pack(s[8 * t + 6], s[8 * t + 7]);
  }
}
template <int C, bool INI> __device__ __forceinline__ void pv(float (&o)[12], const uint32_t (&p)[4][4], uint32_t vlo, uint32_t vhi, int cmin, uint32_t zlo) {
  const bool ok = C >= cmin;
  const uint32_t lo = ok ? vlo + (8 << 16) + C * 64 : zlo, hi = ok ? vhi - C * 64 : 0u, st = ok ? 16u : 0u;
  if (INI) wrs24_ini<0, 0>(o, p[0], lo, hi); else wrs24_acc<0, 0>(o, p[0], lo, hi);
  wrs24_acc<0, 0>(o, p[1], lo + st, hi - st);
  wrs24_acc<0, 0>(o, p[2], lo + 2 * st, hi - 2 * st);
  wrs24_acc<0, 0>(o, p[3], lo + 3 * st, hi - 3 * st);
}
template <int C> __device__ __forceinline__ void qk(float (&s)[32], const uint32_t (&q)[4], uint32_t klo) {
  wrs64_ini<(8 << 16) + C * 128, 0>(s, q, klo, 16u);
}

__device__ __noinline__ uint4 attn_slow(uint32_t q0, uint32_t q1, uint32_t q2, uint32_t q3, uint32_t kv, int a, int warp, int cmin) {
  const int lane = threadIdx.x & 31, r = lane >> 1, half = lane & 1;
  float q[16];
#pragma unroll
  for (int c = 0; c < 4; c++) {
    const int src = (r & 7) * 4 + c;
    uint32_t x0 = __shfl_sync(~0u, q0, src), x1 = __shfl_sync(~0u, q1, src), x2 = __shfl_sync(~0u, q2, src), x3 = __shfl_sync(~0u, q3, src);
    uint32_t lo = (r & 8) ? x1 : x0, hi = (r & 8) ? x3 : x2;
    q[2 * c] = bf_lo(lo); q[2 * c + 1] = bf_hi(lo); q[8 + 2 * c] = bf_lo(hi); q[9 + 2 * c] = bf_hi(hi);
  }
  const int i = 16 * warp + r;
  int j0 = i + 1; if (j0 < 64 * cmin) j0 = 64 * cmin;
  const int j1 = i + 256;
  float m = -INFINITY, l = 0.f, o[16];
#pragma unroll
  for (int d = 0; d < 16; d++) o[d] = 0.f;
  for (int pass = 0; pass < 2; pass++) {
    for (int j = j0 + half; j <= j1; j += 2) {
      const int t = 64 * a + j;
      const uint32_t ka = kv + (t >> 3) * 256 + (t & 7) * 16;
      uint4 k0 = lds128u(ka), k1 = lds128u(ka + 128);
      float s = q[0] * bf_lo(k0.x) + q[1] * bf_hi(k0.x) + q[2] * bf_lo(k0.y) + q[3] * bf_hi(k0.y) + q[4] * bf_lo(k0.z) + q[5] * bf_hi(k0.z) + q[6] * bf_lo(k0.w) + q[7] * bf_hi(k0.w)
              + q[8] * bf_lo(k1.x) + q[9] * bf_hi(k1.x) + q[10] * bf_lo(k1.y) + q[11] * bf_hi(k1.y) + q[12] * bf_lo(k1.z) + q[13] * bf_hi(k1.z) + q[14] * bf_lo(k1.w) + q[15] * bf_hi(k1.w);
      if (pass == 0) m = fmaxf(m, s);
      else {
        const float p = ex2(s - m); l += p;
        uint4 v0 = lds128u(kv + 12288 + (t >> 3) * 128 + (t & 7) * 16);
        uint4 v1 = lds128u(kv + 12288 + 6144 + 256 + (23 - (t >> 4)) * 256 + ((t >> 3) & 1) * 128 + (t & 7) * 16);
        o[0] += p * bf_lo(v0.x); o[1] += p * bf_hi(v0.x); o[2] += p * bf_lo(v0.y); o[3] += p * bf_hi(v0.y);
        o[4] += p * bf_lo(v0.z); o[5] += p * bf_hi(v0.z); o[6] += p * bf_lo(v0.w); o[7] += p * bf_hi(v0.w);
        o[8] += p * bf_lo(v1.x); o[9] += p * bf_hi(v1.x); o[10] += p * bf_lo(v1.y); o[11] += p * bf_hi(v1.y);
        o[12] += p * bf_lo(v1.z); o[13] += p * bf_hi(v1.z); o[14] += p * bf_lo(v1.w); o[15] += p * bf_hi(v1.w);
      }
    }
    if (pass == 0) m = fmaxf(m, __shfl_xor_sync(~0u, m, 1));
  }
  l += __shfl_xor_sync(~0u, l, 1);
  const float inv = 1.f / l;
#pragma unroll
  for (int d = 0; d < 16; d++) o[d] = (o[d] + __shfl_xor_sync(~0u, o[d], 1)) * inv;
  uint32_t pk[8];
#pragma unroll
  for (int d = 0; d < 8; d++) pk[d] = pack(o[2 * d], o[2 * d + 1]);
  uint4 w = make_uint4(0u, 0u, 0u, 0u);
#pragma unroll
  for (int c = 0; c < 4; c++) {
    const uint32_t x0 = __shfl_sync(~0u, pk[c], (lane >> 2) * 2), x1 = __shfl_sync(~0u, pk[c], (lane >> 2) * 2 + 16);
    const uint32_t x2 = __shfl_sync(~0u, pk[4 + c], (lane >> 2) * 2), x3 = __shfl_sync(~0u, pk[4 + c], (lane >> 2) * 2 + 16);
    if ((lane & 3) == c) w = make_uint4(x0, x1, x2, x3);
  }
  return w;
}

struct Params {
  CUtensorMap tx, twqkv, tw1, tw2a, tw2b, two, txt, tout;
  const __nv_bfloat16 *x, *wqkv, *wo, *w1, *b1, *w2, *b2;
  Scratch* scr;
  const void* ones;
};

__device__ __forceinline__ void warp_arrive(uint32_t bar, int lane) { __syncwarp(); if (lane == 0) mbar_arrive(bar); }

__device__ __forceinline__ int w1_slot(int u) { return (int)((0x3210321054321054ull >> ((u - 8) * 4)) & 15); }

template <int NT> __device__ __forceinline__ void h_epilogue(const float (&acc)[NT * 4], uint32_t cbp, float rr0, float mr0, float rr1, float mr1,
                                                             uint32_t keep, uint32_t* dst) {
#pragma unroll
  for (int j = 0; j < NT; j++) {
    const float4 c = lds128(cbp + j * 64);
    const float a0 = gelu_half(__fmaf_rn(acc[4 * j], rr0, __fmaf_rn(mr0, c.x, c.z)));
    const float a1 = gelu_half(__fmaf_rn(acc[4 * j + 1], rr0, __fmaf_rn(mr0, c.y, c.w)));
    const float a2 = gelu_half(__fmaf_rn(acc[4 * j + 2], rr1, __fmaf_rn(mr1, c.x, c.z)));
    const float a3 = gelu_half(__fmaf_rn(acc[4 * j + 3], rr1, __fmaf_rn(mr1, c.y, c.w)));
    uint32_t* p = dst + (j >> 1) * 512 + (j & 1) * 32;
    p[0] = j < 4 ? pack(a0, a1) & keep : pack(a0, a1); p[64] = j < 4 ? pack(a2, a3) & keep : pack(a2, a3);
  }
}

__global__ void __launch_bounds__(NTHR, 1) fused_kernel(const __grid_constant__ Params P) {
  extern __shared__ __align__(1024) uint8_t smem[];
  const uint32_t sb = (uint32_t)__cvta_generic_to_shared(smem);
  const int tid = threadIdx.x, lane = tid & 31;
  const int wid = __shfl_sync(~0u, tid >> 5, 0);
  const int wg = wid >> 2, warp = wid & 3;
  const int b = blockIdx.x;
  const int rb = (b >> 5) * 4 + (b & 3), g = (b >> 2) & 7;
  const int r64 = b >> 2, cb = b & 3;
  const int wbase = min(g * 176, 1200);
  auto BAR = [&](int i) { return sb + OFF_BAR + i * 8; };
  uint32_t epoch = 0;

  if (lane == 0) {
    const int k0 = ((wid + 4) & 15) * 8;
    const int cnt = (int)((0x4444881188881111ull >> (k0 >> 1)) & 15);
#pragma unroll
    for (int e = 0; e < 8; e++) mbar_init(BAR(k0 + e), cnt);
    asm volatile("fence.mbarrier_init.release.cluster;" ::: "memory");
  }
  if (wid == 0) { sts32u(sb + OFF_ZERO + lane * 4, 0u); fence_async_shared(); }
  __syncwarp();
  if (wid == 12) {
#pragma unroll
    for (int u = 0; u < 3; u++) {
      mbar_expect(BAR(B_UF + u), 16384 + 2 * WSLOT);
      tma2d(sb + OFF_X + u * 16384, &P.tx, BAR(B_UF + u), u * 64, rb * 128);
      tma4d(sb + OFF_WS + u * 2 * WSLOT, &P.twqkv, BAR(B_UF + u), 0, u * 64, g, 0);
    }
  }
  asm volatile("ld.relaxed.gpu.global.u32 %0, [%1];" : "=r"(epoch) : "l"(&P.scr->G[g].epoch[rb]) : "memory");
  __syncthreads();
  const int grow = lane >> 2, c2 = (lane & 3) * 2;

  if (wg < 2) {
    asm volatile("setmaxnreg.inc.sync.aligned.u32 152;");
    const int a = wg;
    uint32_t qf[4][4];
    const uint32_t alo = dlo(sb + OFF_X + a * 8192) | (1u << 16);
    float2 s0, s1;
    {
      float acc[96];
      mbar_wait(BAR(B_UF), 0);
      int sl = 0;
#pragma unroll 1
      for (int kb = 0; kb < 8; kb++) {
        const uint32_t al = alo + kb * 1024, bl = dlo(sb + OFF_WS + sl * 2 * WSLOT) | (512u << 16);
        wg_fence();
        wss192<0, HI_SW128, 0, HI_SW128>(acc, al, bl, kb); wg_commit();
        wg_wait<1>();
        if (kb > 0 && lane == 0) mbar_arrive(BAR(B_UE + kb - 1));
        wss192<2, HI_SW128, 128, HI_SW128>(acc, al, bl, 1);
        wss192<4, HI_SW128, 256, HI_SW128>(acc, al, bl, 1); wss192<6, HI_SW128, 384, HI_SW128>(acc, al, bl, 1);
        wg_commit();
        if (kb < 7) mbar_wait(BAR(B_UF + kb + 1), 0);
        if (++sl == 3) sl = 0;
      }
      if (lane == 0) mbar_arrive(BAR(B_QD));
      mbar_wait(BAR(B_PREP), 0);
      s0 = lds64(sb + OFF_ST + (a * 64 + warp * 16 + grow) * 8); s1 = lds64(sb + OFF_ST + (a * 64 + warp * 16 + grow + 8) * 8);
      wg_wait<0>(); pin(acc);
      if (lane == 0) mbar_arrive(BAR(B_UE + 7));
      const uint32_t cq = sb + OFF_CS + c2 * 4;
      const int tg = rb * 16 + a * 8 + warp * 2;
      uint32_t* kp = reinterpret_cast<uint32_t*>(P.scr->G[g].k + tg * 256) + lane;
      uint32_t* v0p = reinterpret_cast<uint32_t*>(P.scr->G[g].v0 + tg * 128) + lane;
      uint32_t* v1p = reinterpret_cast<uint32_t*>(P.scr->G[g].v1 + (127 - (tg >> 1)) * 256) + lane;
#pragma unroll
      for (int j = 8; j < 24; j++) {
        const float2 c = lds64(cq + j * 32);
        const uint32_t u0 = pack(__fmaf_rn(-s0.x, c.x, acc[4 * j]) * s0.y, __fmaf_rn(-s0.x, c.y, acc[4 * j + 1]) * s0.y);
        const uint32_t u1 = pack(__fmaf_rn(-s1.x, c.x, acc[4 * j + 2]) * s1.y, __fmaf_rn(-s1.x, c.y, acc[4 * j + 3]) * s1.y);
        const int i = (j & 7) >> 1;
        if (j < 16) { kp[i * 16384 + (j & 1) * 32] = u0; kp[i * 16384 + 64 + (j & 1) * 32] = u1; }
        else if ((j & 1) == 0) { v0p[i * 8192] = u0; v0p[i * 8192 + 32] = u1; }
        else { v1p[i * 8192] = u0; v1p[i * 8192 + 32] = u1; }
      }
      warp_arrive(BAR(B_KD), lane);
      const float qs0 = s0.y * (0.25f * 1.4426950409f), qs1 = s1.y * (0.25f * 1.4426950409f);
#pragma unroll
      for (int j = 0; j < 8; j++) {
        const float2 c = lds64(cq + j * 32);
        qf[j >> 1][(j & 1) * 2] = pack(__fmaf_rn(-s0.x, c.x, acc[4 * j]) * qs0, __fmaf_rn(-s0.x, c.y, acc[4 * j + 1]) * qs0);
        qf[j >> 1][(j & 1) * 2 + 1] = pack(__fmaf_rn(-s1.x, c.x, acc[4 * j + 2]) * qs1, __fmaf_rn(-s1.x, c.y, acc[4 * j + 3]) * qs1);
      }
      warp_arrive(BAR(B_QR), lane);
    }
    {
      float acc[40];
      mbar_wait(BAR(B_UF + UA0), 0);
#pragma unroll 1
      for (int kb = 0; kb < 8; kb++) {
        const uint32_t al = alo + kb * 1024, bl = dlo(sb + OFF_WS + w1_slot(UA0 + kb) * WSLOT) | (256u << 16);
        wg_fence();
        wss80<0, HI_SW128, 0, HI_SW64>(acc, al, bl, kb); wss80<2, HI_SW128, 64, HI_SW64>(acc, al, bl, 1);
        wss80<4, HI_SW128, 128, HI_SW64>(acc, al, bl, 1); wss80<6, HI_SW128, 192, HI_SW64>(acc, al, bl, 1);
        wg_commit();
        if (kb < 7) mbar_wait(BAR(B_UF + UA0 + 1 + kb), 0);
        wg_wait<1>();
        if (kb > 0 && lane == 0) mbar_arrive(BAR(B_UE + UA0 - 1 + kb));
      }
      const float rr0 = 0.5f * s0.y * rsqrtf(1.f - LN_EPS * s0.y * s0.y + LN_EPS), rr1 = 0.5f * s1.y * rsqrtf(1.f - LN_EPS * s1.y * s1.y + LN_EPS);
      mbar_wait(BAR(B_CB), 0);
      wg_wait<0>(); pin(acc);
      if (lane == 0) mbar_arrive(BAR(B_UE + UA0 + 7));
      h_epilogue<10>(acc, sb + OFF_CB1 + (lane & 3) * 16, rr0, -s0.x * rr0, rr1, -s1.x * rr1, g == 7 ? 0u : ~0u,
                     reinterpret_cast<uint32_t*>(P.scr->R[rb * 2 + a].a2 + g * 11 * 2048 + warp * 512) + lane);
      warp_arrive(BAR(B_XA), lane);
    }
    const int q0 = rb * 128 + a * 64;
    const int cmin = q0 >= 256 ? 0 : (256 - q0) >> 6;
    const int wa = warp - (c2 > grow ? 1 : 0), wb = warp - (c2 + 1 > grow ? 1 : 0);
    const uint32_t vhi = (6144u - a * 1024u) >> 4, zlo = dlo(sb + OFF_ZERO);
    uint4* llp = &P.scr->R[rb * 2 + a].ll[0][g * 128 + (tid & 127)];
#pragma unroll 1
    for (int i = 0; i < 4; i++) {
      const uint32_t kv = sb + ((i & 1) ? OFF_KVB : OFF_KVA);
      const uint32_t klo = dlo(kv + a * 2048), vlo = dlo(kv + 12288 + a * 1024);
      float sA[32], sB[32], o[12]; uint32_t pA[4][4], pB[4][4], pC[4][4];
      mbar_wait(BAR(B_KVF + i), 0);
      wg_fence(); qk<0>(sB, qf[0], klo); qk<4>(sA, qf[0], klo); wg_commit();
      wg_wait<0>(); pin(sA); pin(sB);
#pragma unroll
      for (int t = 0; t < 4; t++) {
        const bool a0 = t > wa, a1 = t > wb, bb = t > warp, cc = t >= warp;
        sB[8 * t] = a0 ? sB[8 * t] : sA[8 * t]; sB[8 * t + 1] = a1 ? sB[8 * t + 1] : sA[8 * t + 1];
        sB[8 * t + 2] = bb ? sB[8 * t + 2] : sA[8 * t + 2]; sB[8 * t + 3] = bb ? sB[8 * t + 3] : sA[8 * t + 3];
        sB[8 * t + 4] = cc ? sB[8 * t + 4] : sA[8 * t + 4]; sB[8 * t + 5] = cc ? sB[8 * t + 5] : sA[8 * t + 5];
        sB[8 * t + 6] = a0 ? sB[8 * t + 6] : sA[8 * t + 6]; sB[8 * t + 7] = a1 ? sB[8 * t + 7] : sA[8 * t + 7];
      }
      wg_fence(); qk<1>(sA, qf[0], klo); wg_commit();
      exps(sB);
      packp(sB, pA);
#pragma unroll
      for (int t = 0; t < 4; t++) {
        const uint32_t ma = (t > wa ? 0x0000FFFFu : 0u) | (t > wb ? 0xFFFF0000u : 0u); const bool bb = t > warp, cc = t >= warp;
        pB[t][0] = pA[t][0] & ma; pA[t][0] &= ~ma;
        pB[t][1] = bb ? pA[t][1] : 0u; pA[t][1] = bb ? 0u : pA[t][1];
        pB[t][2] = cc ? pA[t][2] : 0u; pA[t][2] = cc ? 0u : pA[t][2];
        pB[t][3] = pA[t][3] & ma; pA[t][3] &= ~ma;
      }
      wg_fence(); pv<4, true>(o, pA, vlo, vhi, cmin, zlo); pv<0, false>(o, pB, vlo, vhi, cmin, zlo); wg_commit();
      wg_wait<1>(); pin(sA);
      exps(sA); packp(sA, pC);
      wg_fence(); qk<2>(sA, qf[0], klo); wg_commit();
      wg_fence(); pv<1, false>(o, pC, vlo, vhi, cmin, zlo); wg_commit();
      wg_wait<1>(); pin(sA);
      wg_fence(); qk<3>(sB, qf[0], klo); wg_commit();
      exps(sA); packp(sA, pA);
      wg_fence(); pv<2, false>(o, pA, vlo, vhi, cmin, zlo); wg_commit();
      wg_wait<1>(); pin(sB);
      exps(sB); packp(sB, pB);
      wg_fence(); pv<3, false>(o, pB, vlo, vhi, cmin, zlo); wg_commit();
      wg_wait<0>(); pin(o);
      const bool unsafe = !(o[4] < 1.0995116e12f && o[4] > 9.094947e-13f && o[6] < 1.0995116e12f && o[6] > 9.094947e-13f);
      float inv0, inv1;
      asm("rcp.approx.ftz.f32 %0, %1;" : "=f"(inv0) : "f"(o[4])); asm("rcp.approx.ftz.f32 %0, %1;" : "=f"(inv1) : "f"(o[6]));
      uint4 of = make_uint4(pack(o[0] * inv0, o[1] * inv0), pack(o[2] * inv1, o[3] * inv1), pack(o[8] * inv0, o[9] * inv0), pack(o[10] * inv1, o[11] * inv1));
      if (__any_sync(~0u, unsafe)) of = attn_slow(qf[0][0], qf[0][1], qf[0][2], qf[0][3], kv, a, warp, cmin);
      if (i == 3) {
        asm volatile("st.relaxed.gpu.global.v4.u32 [%0], {%1,%2,%3,%4};" ::"l"(llp + (epoch & 1) * 1024),
                     "r"(of.x ? of.x : 0x8000u), "r"(of.y ? of.y : 0x8000u), "r"(of.z ? of.z : 0x8000u), "r"(of.w ? of.w : 0x8000u) : "memory");
        llp[(~epoch & 1) * 1024] = make_uint4(0u, 0u, 0u, 0u);
        return;
      }
      uint32_t* op = reinterpret_cast<uint32_t*>(P.scr->R[rb * 2 + a].a2 + (88 + i * 8 + g) * 2048 + warp * 512) + lane;
      op[0] = of.x; op[32] = of.z; op[64] = of.y; op[96] = of.w;
      warp_arrive(BAR(B_OD + i), lane);
#pragma unroll
      for (int n = 0; n < 3; n++) {
#pragma unroll
        for (int e = 0; e < 4; e++) qf[n][e] = qf[n + 1][e];
      }
    }
  } else if (wg == 2) {
    asm volatile("setmaxnreg.inc.sync.aligned.u32 144;");
    {
      const int t = tid & 127;
      uint4 xw[8];
      const __nv_bfloat16* xp = P.x + (size_t)(rb * 128 + g * 16 + (t >> 3)) * D_ + (t & 7) * 8;
#pragma unroll 1
      for (int job = 0; job < 2; job++) {
        const int jb = job ? b - 42 : b, ld = job ? 1376 : 1536;
        const bool act = job ? jb >= 0 : jb < 96;
        uint4 w[8];
        if (job) mbar_wait(BAR(B_UF + 1), 0);
        if (act) {
          const __nv_bfloat16* wp = (job ? P.w1 : P.wqkv) + (jb >> 1) * 32 + (size_t)((jb & 1) * 256 + (t >> 2)) * ld + (t & 3) * 8;
#pragma unroll
          for (int r = 0; r < 8; r++) w[r] = ldg128(wp + (size_t)r * 32 * ld);
        }
        if (job == 0) {
#pragma unroll
          for (int r = 0; r < 8; r++) xw[r] = ldg128(xp + r * 64);
        } else {
          float sa[4] = {0.f, 0.f, 0.f, 0.f}, qa[4] = {0.f, 0.f, 0.f, 0.f};
#pragma unroll
          for (int r = 0; r < 8; r++) {
            const uint32_t u[4] = {xw[r].x, xw[r].y, xw[r].z, xw[r].w};
#pragma unroll
            for (int e = 0; e < 4; e++) {
              const float d0 = bf_lo(u[e]), d1 = bf_hi(u[e]);
              sa[e] += d0 + d1; qa[e] = __fmaf_rn(d0, d0, __fmaf_rn(d1, d1, qa[e]));
            }
          }
          float sx = (sa[0] + sa[1]) + (sa[2] + sa[3]), qx = (qa[0] + qa[1]) + (qa[2] + qa[3]);
#pragma unroll
          for (int o = 1; o < 8; o <<= 1) { sx += __shfl_xor_sync(~0u, sx, o); qx += __shfl_xor_sync(~0u, qx, o); }
          const float mean = sx * (1.f / D_);
          const float rstd = rsqrtf(fmaxf(__fmaf_rn(-mean, mean, qx * (1.f / D_)), 0.f) + LN_EPS);
          if ((t & 7) == 0)
            asm volatile("{\n.reg .b64 a, b;\nmov.b64 a, {%1,%2};\nmov.b64 b, {%3,%2};\nst.relaxed.gpu.global.v2.b64 [%0], {a, b};\n}" ::"l"(&P.scr->R[rb * 2 + (g >> 2)].stat[(g & 3) * 16 + (t >> 3)]), "r"(__float_as_uint(mean)), "r"(~epoch), "r"(__float_as_uint(rstd)) : "memory");
        }
        if (act) {
          float c8[8];
#pragma unroll
          for (int e = 0; e < 8; e++) c8[e] = 0.f;
#pragma unroll
          for (int r = 0; r < 8; r++) {
            c8[0] += bf_lo(w[r].x); c8[1] += bf_hi(w[r].x); c8[2] += bf_lo(w[r].y); c8[3] += bf_hi(w[r].y);
            c8[4] += bf_lo(w[r].z); c8[5] += bf_hi(w[r].z); c8[6] += bf_lo(w[r].w); c8[7] += bf_hi(w[r].w);
          }
#pragma unroll
          for (int e = 0; e < 4; e++) { const bool hi = lane & 16; const float snd = hi ? c8[e] : c8[e + 4]; c8[e] = (hi ? c8[e + 4] : c8[e]) + __shfl_xor_sync(~0u, snd, 16); }
#pragma unroll
          for (int e = 0; e < 2; e++) { const bool hi = lane & 8; const float snd = hi ? c8[e] : c8[e + 2]; c8[e] = (hi ? c8[e + 2] : c8[e]) + __shfl_xor_sync(~0u, snd, 8); }
          { const bool hi = lane & 4; const float snd = hi ? c8[0] : c8[1]; c8[0] = (hi ? c8[1] : c8[0]) + __shfl_xor_sync(~0u, snd, 4); }
          const uint32_t red = sb + OFF_RED + job * 512;
          sts32u(red + (warp * 32 + (lane & 3) * 8 + (lane >> 2)) * 4, __float_as_uint(c8[0]));
          asm volatile("bar.sync 2, 128;" ::: "memory");
          if (warp == 0) {
            const uint32_t ra = red + lane * 4;
            const float tot = (__uint_as_float(lds32u(ra)) + __uint_as_float(lds32u(ra + 128))) + (__uint_as_float(lds32u(ra + 256)) + __uint_as_float(lds32u(ra + 384)));
            asm volatile("{\n.reg .b64 a;\nmov.b64 a, {%1,%2};\nst.relaxed.gpu.global.b64 [%0], a;\n}" ::"l"(&P.scr->cs[(job * 1536 + (jb >> 1) * 32 + lane) * 2 + (jb & 1)]), "r"(__float_as_uint(tot)), "r"(~epoch) : "memory");
          }
        }
      }
    }
    float rr[4], mr[4];
    mbar_wait(BAR(B_PREP), 0);
#pragma unroll
    for (int e = 0; e < 4; e++) {
      const float2 st = lds64(sb + OFF_ST + ((e >> 1) * 64 + warp * 16 + grow + (e & 1) * 8) * 8);
      rr[e] = 0.5f * st.y * rsqrtf(1.f - LN_EPS * st.y * st.y + LN_EPS);
      mr[e] = -st.x * rr[e];
    }
    warp_arrive(BAR(B_SR), lane);
    {
      const uint32_t alo = dlo(sb + OFF_X) | (1u << 16);
      float acc0[48], acc1[48];
#define W1R(AO, K, SD, A) wss96<(AO) + 2 * (K), HI_SW128, 64 * (K), HI_SW64>(A, al, bl, SD);
      mbar_wait(BAR(B_UF + 8), 0);
      mbar_wait(BAR(B_QD), 0);
#pragma unroll 1
      for (int kb = 0; kb < 8; kb++) {
        const int u = kb < NG0 ? 8 + kb : 16 + kb;
        const uint32_t al = alo + kb * 1024, bl = dlo(sb + OFF_WS + w1_slot(u) * WSLOT) | (256u << 16);
        wg_fence();
        W1R(0, 0, kb, acc0) W1R(512, 0, kb, acc1) W1R(0, 1, 1, acc0) W1R(512, 1, 1, acc1)
        W1R(0, 2, 1, acc0) W1R(512, 2, 1, acc1) W1R(0, 3, 1, acc0) W1R(512, 3, 1, acc1)
        wg_commit(); wg_wait<1>();
        if (lane == 0 && kb > 0 && kb != NG0) mbar_arrive_n<2>(BAR(B_UE + u - 1));
        if (kb == NG0 - 1) { wg_wait<0>(); if (lane == 0) mbar_arrive_n<2>(BAR(B_UE + UA0 - 1)); }
        if (kb < 7) mbar_wait(BAR(B_UF + (kb == NG0 - 1 ? UA0 + 8 : u + 1)), 0);
      }
      mbar_wait(BAR(B_CB), 0);
      wg_wait<0>(); pin(acc0); pin(acc1);
      if (lane == 0) mbar_arrive(BAR(B_XF));
#pragma unroll 1
      for (int hf = 0; hf < 2; hf++) {
        h_epilogue<12>(acc0, sb + OFF_CB1 + 640 + (lane & 3) * 16, rr[0], mr[0], rr[1], mr[1], ~0u,
                       reinterpret_cast<uint32_t*>(P.scr->R[rb * 2 + hf].a2 + (g * 11 + 5) * 2048 + warp * 512) + lane);
        warp_arrive(BAR(B_HD + hf), lane);
#pragma unroll
        for (int j = 0; j < 48; j++) acc0[j] = acc1[j];
        rr[0] = rr[2]; rr[1] = rr[3]; mr[0] = mr[2]; mr[1] = mr[3];
      }
    }
    float acc[64];
#define G2K(K, SD) wss128<(K) * 128, HI_A2, (K) * 128, HI_SW128>(acc, al, bl, SD); wg_commit(); wg_wait<2>();
#define G2_STAGE(NS)                                                                                          \
    {                                                                                                         \
      const uint32_t bl = dlo(sb + (s & 3) * G2SLOT) | ((NS * 128u) << 16), al = dlo(sb + (s & 3) * G2SLOT + 24576) | (8u << 16); \
      wg_fence();                                                                                             \
      G2K(0, s) G2K(1, 1)                                                                                     \
      if (s > 0 && lane == 0) mbar_arrive(BAR(B_G2E + ((s - 1) & 3)));                                        \
      G2K(2, 1)                                                                                               \
      if (NS > 4) { G2K(3, 1) }                                                                               \
      if (NS > 5) { G2K(4, 1) }                                                                               \
      wss128<(NS - 1) * 128, HI_A2, (NS - 1) * 128, HI_SW128>(acc, al, bl, 1); wg_commit();                   \
      s++;                                                                                                    \
      if (s != 20) mbar_wait(BAR(B_G2F + (s & 3)), (s >> 2) & 1);                                             \
    }
    const uint32_t orow = sb + OFF_OUT + (warp * 16 + (lane & 15)) * 128;
    mbar_wait(BAR(B_G2F), 0);
    {
      int s = 0;
#pragma unroll 1
      do G2_STAGE(5) while (s < 8);
#pragma unroll 1
      do {
        if (s == 10) {
#pragma unroll 1
          do G2_STAGE(6) while (s < 18);
        }
        G2_STAGE(4)
        if (s == 20) {
          mbar_wait(BAR(B_XT), 0);
          wg_wait<0>(); pin(acc);
#pragma unroll
          for (int j = 0; j < 16; j += 2) {
            uint32_t x0, x1, x2, x3;
            asm volatile("ldmatrix.sync.aligned.m8n8.x4.shared.b16 {%0,%1,%2,%3}, [%4];" : "=r"(x0), "=r"(x1), "=r"(x2), "=r"(x3)
                         : "r"(orow + (j >> 3) * 8192 + ((((j & 7) + (lane >> 4)) ^ (lane & 7)) << 4)));
            const float2 b0 = lds64(sb + OFF_B2 + (j * 8 + c2) * 4), b1 = lds64(sb + OFF_B2 + (j * 8 + 8 + c2) * 4);
            acc[4 * j] += bf_lo(x0) + b0.x; acc[4 * j + 1] += bf_hi(x0) + b0.y; acc[4 * j + 2] += bf_lo(x1) + b0.x; acc[4 * j + 3] += bf_hi(x1) + b0.y;
            acc[4 * j + 4] += bf_lo(x2) + b1.x; acc[4 * j + 5] += bf_hi(x2) + b1.y; acc[4 * j + 6] += bf_lo(x3) + b1.x; acc[4 * j + 7] += bf_hi(x3) + b1.y;
          }
          pin(acc);
          mbar_wait(BAR(B_G2F), 1);
        }
      } while (s < 22);
    }
    {
      uint32_t af[8][4];
      const uint4* lp = &P.scr->R[r64].ll[epoch & 1][tid & 127];
      mbar_wait(BAR(B_G2F + 3), 1);
      uint32_t it = 0;
      while (true) {
        bool ok = true;
#pragma unroll
        for (int e = 0; e < 8; e++) { const uint4 v = ld_rlx4(lp + e * 128); af[e][0] = v.x; af[e][1] = v.y; af[e][2] = v.z; af[e][3] = v.w; }
#pragma unroll
        for (int e = 0; e < 8; e++) ok = ok && af[e][0] && af[e][1] && af[e][2] && af[e][3];
        if (__all_sync(~0u, ok)) break;
        if (++it > SPIN_LIMIT) __trap();
      }
      const uint32_t bl = dlo(sb + 2 * G2SLOT) | (512u << 16);
      wg_wait<0>();
      wg_fence();
      wrs128<0, HI_SW128>(acc, af[0], bl, 1); wrs128<128, HI_SW128>(acc, af[1], bl, 1); wrs128<256, HI_SW128>(acc, af[2], bl, 1); wrs128<384, HI_SW128>(acc, af[3], bl, 1);
      wrs128<(G2SLOT >> 4), HI_SW128>(acc, af[4], bl, 1); wrs128<(G2SLOT >> 4) + 128, HI_SW128>(acc, af[5], bl, 1);
      wrs128<(G2SLOT >> 4) + 256, HI_SW128>(acc, af[6], bl, 1); wrs128<(G2SLOT >> 4) + 384, HI_SW128>(acc, af[7], bl, 1);
      wg_commit();
    }
    wg_wait<0>(); pin(acc);
    if (lane == 0) mbar_arrive(BAR(B_DONE));
    {
#pragma unroll
      for (int j = 0; j < 16; j += 2) {
        const uint32_t ad = orow + (j >> 3) * 8192 + ((((j & 7) + (lane >> 4)) ^ (lane & 7)) << 4);
        asm volatile("stmatrix.sync.aligned.m8n8.x4.shared.b16 [%0], {%1,%2,%3,%4};" ::"r"(ad),
                     "r"(pack(acc[4 * j], acc[4 * j + 1])), "r"(pack(acc[4 * j + 2], acc[4 * j + 3])),
                     "r"(pack(acc[4 * j + 4], acc[4 * j + 5])), "r"(pack(acc[4 * j + 6], acc[4 * j + 7])) : "memory");
      }
    }
    fence_async_shared();
    __syncwarp();
    if (lane == 0) {
      tma3d_store(&P.tout, sb + OFF_OUT + warp * 2048, 0, r64 * 64 + warp * 16, cb * 2);
      tma3d_store(&P.tout, sb + OFF_OUT + 8192 + warp * 2048, 0, r64 * 64 + warp * 16, cb * 2 + 1);
      asm volatile("cp.async.bulk.commit_group;" ::: "memory");
      if (warp == 0) P.scr->G[g].epoch[rb] = epoch + 1;
      asm volatile("cp.async.bulk.wait_group.read 0;" ::: "memory");
    }
  } else {
    asm volatile("setmaxnreg.dec.sync.aligned.u32 64;");
    const uint32_t ep1 = epoch + 1;
    if (warp == 0) {
#pragma unroll 1
      for (int u = 3; u < 8; u++) {
        const uint32_t fb = BAR(B_UF + u);
        mbar_expect(fb, 16384 + 2 * WSLOT);
        mbar_wait(BAR(B_UF + u - 3), 0);
        tma2d(sb + OFF_X + u * 16384, &P.tx, fb, u * 64, rb * 128);
        mbar_wait(BAR(B_UE + u - 3), 0);
        tma4d(sb + OFF_WS + (u < 6 ? u - 3 : u - 6) * 2 * WSLOT, &P.twqkv, fb, 0, u * 64, g, 0);
      }
#pragma unroll 1
      for (int u = 8; u < 24; u++) {
        const uint32_t fb = BAR(B_UF + u);
        const bool au = u >= UA0 && u < UA0 + 8;
        mbar_expect(fb, WSLOT);
        mbar_wait(BAR(B_UE + (u < 14 ? 1 + (u >> 1) : u - (u < 20 ? 6 : 4))), 0);
        tma3d(sb + OFF_WS + w1_slot(u) * WSLOT, &P.tw1, fb, wbase + (au ? 0 : 80), (au ? u - UA0 : u & 7) * 64, 0);
      }
      mbar_wait(BAR(B_XF), 0);
      mbar_wait(BAR(B_UE + UA0 + 7), 0);
#pragma unroll
      for (int s = 0; s < 24; s++) {
        const uint32_t fb = BAR(B_G2F + (s & 3)), dst = sb + (s & 3) * G2SLOT;
        const bool hb = s >= 10 && s < 18;
        const int row = min((hb ? s - 10 : s) * 176, 1200) + (hb ? 80 : 0);
        mbar_wait(BAR(B_G2E + (s & 3)), ((s >> 2) & 1) ^ 1);
        mbar_expect(fb, s < 8 ? 5 * 6144 : hb ? 6 * 6144 : s < 22 ? 4 * 6144 : 4 * 4096);
        if (s < 8 || hb) tma3d(dst, hb ? &P.tw2a : &P.tw2b, fb, 0, row, cb * 2);
        else tma5d(dst, &P.two, fb, 0, 0, s < 10 ? 0 : (s - 16) >> 1, (s & 1) * 4, cb * 2);
      }
    } else if (warp == 1) {
      {
        uint4 v[6]; uint32_t it = 0;
        mbar_wait(BAR(B_UF + 1), 0);
        while (true) {
          uint32_t bad = 0;
#pragma unroll
          for (int e = 0; e < 6; e++) v[e] = ld_rlx4(reinterpret_cast<const uint4*>(P.scr->cs) + (e >> 1) * 512 + g * 64 + (e & 1) * 32 + lane);
#pragma unroll
          for (int e = 0; e < 6; e++) bad |= (v[e].y ^ ~epoch) | (v[e].w ^ ~epoch);
          if (__all_sync(~0u, bad == 0)) break;
          if (++it > SPIN_LIMIT) __trap();
        }
#pragma unroll
        for (int e = 0; e < 6; e++) sts32u(sb + OFF_CS + e * 128 + lane * 4, __float_as_uint(__uint_as_float(v[e].x) + __uint_as_float(v[e].z)));
        __syncwarp();
        if (lane == 0) mbar_arrive_n<4>(BAR(B_PREP));
      }
#pragma unroll 1
      for (int i = 0; i < 5; i++) {
        if (i >= 2) mbar_wait(BAR(B_OD + i - 2), 0);
        if (i < 4) {
          const uint32_t dst = sb + ((i & 1) ? OFF_KVB : OFF_KVA), fb = BAR(B_KVF + i);
          const uint8_t* ksrc = P.scr->G[g].k + i * 65536 + (rb - 2) * 4096;
          const uint8_t* v0src = P.scr->G[g].v0 + i * 32768 + (rb - 2) * 2048;
          const uint8_t* v1src = P.scr->G[g].v1 + i * 32768 + (15 - rb) * 2048;
          mbar_expect(fb, i < 2 ? KVB : KVB - 256);
          if (i < 2) { mbar_wait(BAR(i ? B_UE + 15 : B_SR), 0); bulk_ld(dst + 12288 + 6144, P.ones, 256, fb); }
          if (i == 0) { mbar_wait(BAR(B_QR), 0); cnt_wait(&P.scr->G[g].kvcnt[rb * 8], ep1 * (rb >= 2 ? 3 : rb + 1)); }
          if (rb >= 2) {
            bulk_ld(dst, ksrc, 12288, fb); bulk_ld(dst + 12288, v0src, 6144, fb); bulk_ld(dst + 12288 + 6144 + 256, v1src, 6144, fb);
          } else {
#pragma unroll 1
            for (int c = 0; c < 3; c++) {
              const int sk = rb - 2 + c < 0 ? 2 - rb : c;
              bulk_ld(dst + c * 4096, ksrc + sk * 4096, 4096, fb); bulk_ld(dst + 12288 + c * 2048, v0src + sk * 2048, 2048, fb);
              bulk_ld(dst + 12288 + 6144 + 256 + (2 - c) * 2048, v1src + (2 - sk) * 2048, 2048, fb);
            }
          }
        }
        if (i >= 2 && lane < 2) cnt_add_rel(&P.scr->R[rb * 2 + lane].acnt[i * 8]);
        __syncwarp();
      }
    } else if (warp == 2) {
      {
        uint4 v[4]; uint32_t it = 0;
        mbar_guard(BAR(B_UF + 1));
        while (true) {
          uint32_t bad = 0;
#pragma unroll
          for (int e = 0; e < 4; e++) v[e] = ld_rlx4(&P.scr->R[rb * 2 + (e >> 1)].stat[(e & 1) * 32 + lane]);
#pragma unroll
          for (int e = 0; e < 4; e++) bad |= (v[e].y ^ ~epoch) | (v[e].w ^ ~epoch);
          if (__all_sync(~0u, bad == 0)) break;
          if (++it > SPIN_LIMIT) __trap();
        }
#pragma unroll
        for (int e = 0; e < 4; e++) asm volatile("st.shared.v2.u32 [%0], {%1,%2};" ::"r"(sb + OFF_ST + (e * 32 + lane) * 8), "r"(v[e].x), "r"(v[e].z) : "memory");
        __syncwarp();
        if (lane == 0) mbar_arrive_n<4>(BAR(B_PREP));
      }
#pragma unroll 1
      for (int i = 0; i < 4; i++) {
        mbar_guard(BAR(i == 0 ? B_KD : i == 1 ? B_XA : B_HD + i - 2));
        uint32_t* f = i == 0 ? &P.scr->G[g].kvcnt[(rb + lane) * 8] : i == 1 ? &P.scr->R[rb * 2 + (lane & 1)].acnt[0] : &P.scr->R[rb * 2 + (i & 1)].acnt[8];
        if (lane < (i < 2 ? 3 - i : 1)) cnt_add_rel(f);
        __syncwarp();
      }
      mbar_guard(BAR(B_DONE));
    } else {
      {
        uint32_t it = 0;
#pragma unroll
        for (int e = 0; e < 6; e++) {
          const int c = e * 32 + lane;
          if (c < 176) sts32u(sb + OFF_CB1 + (c >> 1) * 16 + 8 + (c & 1) * 4, __float_as_uint(0.5f * __bfloat162float(P.b1[wbase + c])));
        }
        uint4 v[6];
        mbar_wait(BAR(B_UF + 6), 0);
        while (true) {
          uint32_t bad = 0;
#pragma unroll
          for (int e = 0; e < 6; e++) v[e] = ld_rlx4(reinterpret_cast<const uint4*>(P.scr->cs) + 1536 + wbase + (e < 5 ? e * 32 + lane : 160 + (lane & 15)));
#pragma unroll
          for (int e = 0; e < 6; e++) bad |= (v[e].y ^ ~epoch) | (v[e].w ^ ~epoch);
          if (__all_sync(~0u, bad == 0)) break;
          if (++it > SPIN_LIMIT) __trap();
        }
#pragma unroll
        for (int e = 0; e < 6; e++) {
          const int c = e < 5 ? e * 32 + lane : 160 + (lane & 15);
          sts32u(sb + OFF_CB1 + (c >> 1) * 16 + (c & 1) * 4, __float_as_uint(__uint_as_float(v[e].x) + __uint_as_float(v[e].z)));
        }
        warp_arrive(BAR(B_CB), lane);
      }
      mbar_wait(BAR(B_KVF), 0);
      l2_prefetch(reinterpret_cast<const uint8_t*>(P.w2) + b * 11008, 11008);
      l2_prefetch(reinterpret_cast<const uint8_t*>(P.wo) + b * 4096, 4096);
      mbar_wait(BAR(B_XA), 0);
      const uint8_t* src = P.scr->R[r64].a2;
      const uint32_t* cnt = &P.scr->R[r64].acnt[(lane & 7) * 8];
      uint32_t ready = 0;
      const uint2 b2v = __ldg(reinterpret_cast<const uint2*>(P.b2 + cb * 128) + lane);
      auto poll = [&](uint32_t need) {
        if (!(ready & need)) {
          uint32_t it = 0;
          do {
            ready = __ballot_sync(~0u, ld_acq(cnt) == ep1 * 8);
            if (++it > SPIN_LIMIT) __trap();
          } while (!(ready & need));
          fence_async_global();
        }
      };
#pragma unroll 1
      for (int grp = 0; grp < 5; grp++) {
        poll(1u << ((0x43120 >> (grp * 4)) & 15));
        if (grp == 0) {
          mbar_wait(BAR(B_XF), 0);
          asm volatile("st.shared.v4.f32 [%0], {%1,%2,%3,%4};" ::"r"(sb + OFF_B2 + lane * 16), "f"(bf_lo(b2v.x)), "f"(bf_hi(b2v.x)), "f"(bf_lo(b2v.y)), "f"(bf_hi(b2v.y)) : "memory");
          __syncwarp();
          mbar_expect(BAR(B_XT), 16384);
          tma3d(sb + OFF_OUT, &P.txt, BAR(B_XT), 0, r64 * 64, cb * 2);
        }
        const bool isH = grp == 0 || grp == 2;
        int s = grp == 0 ? 0 : grp == 1 ? 8 : grp == 2 ? 10 : 12 + 2 * grp;
        const int e = s + (isH ? 8 : 2);
        const uint8_t* p = src + (grp == 0 ? 0 : grp == 1 ? 88 : grp == 2 ? 5 : 72 + 8 * grp) * 2048;
        const uint32_t stride = isH ? 11 * 2048 : 4 * 2048, bytes = grp == 0 ? 5 * 2048 : grp == 2 ? 6 * 2048 : 4 * 2048;
#pragma unroll 1
        for (; s < e; s++, p += stride) {
          mbar_wait(BAR(B_G2E + (s & 3)), ((s >> 2) & 1) ^ 1);
          bulk_ld(sb + (s & 3) * G2SLOT + 24576, p, bytes, BAR(B_G2F + (s & 3)));
        }
      }
    }
  }
}

typedef CUresult (*EncFn)(CUtensorMap*, CUtensorMapDataType, cuuint32_t, void*, const cuuint64_t*, const cuuint64_t*, const cuuint32_t*,
                          const cuuint32_t*, CUtensorMapInterleave, CUtensorMapSwizzle, CUtensorMapL2promotion, CUtensorMapFloatOOBfill);

void make_map(EncFn enc, CUtensorMap* m, const void* ptr, int rank, const cuuint64_t* dims, const cuuint64_t* strides, const cuuint32_t* box, CUtensorMapSwizzle sw) {
  const cuuint32_t es[5] = {1, 1, 1, 1, 1};
  enc(m, CU_TENSOR_MAP_DATA_TYPE_BFLOAT16, rank, const_cast<void*>(ptr), dims, strides, box, es, CU_TENSOR_MAP_INTERLEAVE_NONE, sw,
      CU_TENSOR_MAP_L2_PROMOTION_L2_128B, CU_TENSOR_MAP_FLOAT_OOB_FILL_NONE);
}

}

extern "C" void kernel_launch(void* const* d_in, const int* in_sizes, int n_in, void* d_out, int out_size) {
  (void)in_sizes; (void)n_in; (void)out_size;
  static EncFn enc = nullptr;
  static void *scr = nullptr, *ones = nullptr;
  if (!enc) {
    void* fn = nullptr; cudaDriverEntryPointQueryResult qr;
    cudaGetDriverEntryPoint("cuTensorMapEncodeTiled", &fn, cudaEnableDefault, &qr);
    enc = (EncFn)fn;
    cudaGetSymbolAddress(&scr, g_scr);
    cudaGetSymbolAddress(&ones, g_ones);
    cudaFuncSetAttribute(fused_kernel, cudaFuncAttributeMaxDynamicSharedMemorySize, SMEM_BYTES);
  }
  Params P;
  P.scr = (Scratch*)scr; P.ones = ones;
  P.x = (const __nv_bfloat16*)d_in[0]; P.wqkv = (const __nv_bfloat16*)d_in[1]; P.wo = (const __nv_bfloat16*)d_in[2];
  P.w1 = (const __nv_bfloat16*)d_in[4]; P.b1 = (const __nv_bfloat16*)d_in[5]; P.w2 = (const __nv_bfloat16*)d_in[6]; P.b2 = (const __nv_bfloat16*)d_in[7];
  { cuuint64_t d[2] = {512, 2048}, s[1] = {1024}; cuuint32_t bx[2] = {64, 128}; make_map(enc, &P.tx, P.x, 2, d, s, bx, CU_TENSOR_MAP_SWIZZLE_128B); }
  { cuuint64_t d[4] = {64, 512, 8, 3}, s[3] = {3072, 128, 1024}; cuuint32_t bx[4] = {64, 64, 1, 3}; make_map(enc, &P.twqkv, P.wqkv, 4, d, s, bx, CU_TENSOR_MAP_SWIZZLE_128B); }
  { cuuint64_t d[3] = {1312, 512, 3}, s[2] = {2752, 64}; cuuint32_t bx[3] = {32, 64, 3}; make_map(enc, &P.tw1, P.w1, 3, d, s, bx, CU_TENSOR_MAP_SWIZZLE_64B); }
  { cuuint64_t d[3] = {64, 1376, 8}, s[2] = {1024, 128}; cuuint32_t bx[3] = {64, 96, 2}; make_map(enc, &P.tw2a, P.w2, 3, d, s, bx, CU_TENSOR_MAP_SWIZZLE_128B); }
  { cuuint64_t d[3] = {64, 1376, 8}, s[2] = {1024, 128}; cuuint32_t bx[3] = {64, 80, 2}; make_map(enc, &P.tw2b, P.w2, 3, d, s, bx, CU_TENSOR_MAP_SWIZZLE_128B); }
  { cuuint64_t d[5] = {64, 16, 4, 8, 8}, s[4] = {1024, 16384, 65536, 128}; cuuint32_t bx[5] = {64, 16, 1, 4, 2}; make_map(enc, &P.two, P.wo, 5, d, s, bx, CU_TENSOR_MAP_SWIZZLE_128B); }
  { cuuint64_t d[3] = {64, 2048, 8}, s[2] = {1024, 128}; cuuint32_t bx[3] = {64, 64, 2}; make_map(enc, &P.txt, P.x, 3, d, s, bx, CU_TENSOR_MAP_SWIZZLE_128B); }
  { cuuint64_t d[3] = {64, 2048, 8}, s[2] = {1024, 128}; cuuint32_t bx[3] = {64, 16, 1}; make_map(enc, &P.tout, d_out, 3, d, s, bx, CU_TENSOR_MAP_SWIZZLE_128B); }
  fused_kernel<<<NCTA, NTHR, SMEM_BYTES, cudaStreamPerThread>>>(P);
}
```
